```python
import torch

def _softmax(x, axis=-1):
    return torch.softmax(x, dim=axis)

def _gelu(x):
    return torch.nn.functional.gelu(x, approximate='tanh')

def _silu(x):
    return torch.nn.functional.silu(x)

def _sigmoid(x):
    return torch.sigmoid(x)

def _layernorm(x, axis=-1, eps=1e-05):
    m = x.mean(dim=axis, keepdim=True)
    v = x.var(dim=axis, keepdim=True, unbiased=False)
    return (x - m) / torch.sqrt(v + eps)

def _scatter_add(tgt, idx, src, axis=0):
    return tgt.clone().index_add_(axis, idx, src)

def _segment_sum(src, seg, n):
    out = torch.zeros((n,) + src.shape[1:], dtype=src.dtype)
    return out.index_add_(0, seg, src)

def _pad(x, pw):
    flat = tuple((v for pair in reversed(pw) for v in pair))
    return torch.nn.functional.pad(x, flat)
kernel_name = 'adaLN_cond__mha_block_cached__dense_activation_silu__prompt'

def setup_inputs():

    _w = lambda a: (lambda t: t.to(torch.bfloat16) if t.is_floating_point() else t)(torch.as_tensor(a))

    def _A_setup():
        B, Sq, D = (1, 2048, 448)
        H, Sk, Dh = (16, 2048, 256)
        return {'x': _w((lambda *s: torch.randn(*s, dtype=torch.bfloat16) * 0.1)(B, Sq, D)), 'k_cache': _w((lambda *s: torch.randn(*s, dtype=torch.bfloat16) * 0.8)(B, H, Sk, Dh)), 'v_cache': _w((lambda *s: torch.randn(*s, dtype=torch.bfloat16) * 3.2)(B, H, Sk, Dh)), 'wq': _w((lambda *s: torch.randn(*s, dtype=torch.bfloat16) * 0.8)(D, H * Dh) * D ** (-0.5)), 'wo': _w((lambda *s: torch.randn(*s, dtype=torch.bfloat16) * 3.2)(H * Dh, D) * (H * Dh) ** (-0.5))}
    _A_in = _A_setup()

    def _B_setup():
        B, S, D, F = (1, 2048, 448, 1792)
        return {'x': _w((lambda *s: torch.randn(*s, dtype=torch.bfloat16) * 0.1)(B, S, D)), 'w1': _w((lambda *s: torch.randn(*s, dtype=torch.bfloat16) * 3.2)(D, F) * D ** (-0.5)), 'w2': _w((lambda *s: torch.randn(*s, dtype=torch.bfloat16) * 3.2)(F, D) * F ** (-0.5))}
    _B_in = _B_setup()
    return {'A_x': _A_in['x'], 'A_k_cache': _A_in['k_cache'], 'A_v_cache': _A_in['v_cache'], 'A_wq': _A_in['wq'], 'A_wo': _A_in['wo'], 'B_x': _B_in['x'], 'B_w1': _B_in['w1'], 'B_w2': _B_in['w2'], 'c': _w((lambda *s: torch.randn(*s, dtype=torch.bfloat16) * 0.1)(1, 448) * 8.0), 'w_mod': _w((lambda *s: torch.randn(*s, dtype=torch.bfloat16) * 0.1)(448, 6 * 448) * 448 ** (-0.5) * 8.0)}

def reference(A_x, A_k_cache, A_v_cache, A_wq, A_wo, B_x, B_w1, B_w2, c, w_mod):

    def _A_ref(x, k_cache, v_cache, wq, wo):
        B, Sq, D = x.shape
        H, Dh = (16, 256)
        q = (lambda x, *d: x.permute(*d))((x @ wq).reshape(B, Sq, H, Dh), 0, 2, 1, 3)
        scores = torch.einsum('bhqd,bhkd->bhqk', q, k_cache) * Dh ** (-0.5)
        p = _softmax(scores, axis=-1)
        o = torch.einsum('bhqk,bhkd->bhqd', p, v_cache)
        return (lambda x, *d: x.permute(*d))(o, 0, 2, 1, 3).reshape(B, Sq, H * Dh) @ wo

    def _B_ref(x, w1, w2):
        h = torch.einsum('bsd,df->bsf', x, w1)
        h = _silu(h)
        out = torch.einsum('bsf,fd->bsd', h, w2)
        return out
    x = A_x
    mod = (_silu(c) @ w_mod).reshape(c.shape[0], 6, 1, -1)
    sa, ca, ga, sb, cb, gb = (mod[:, 0].clone(), mod[:, 1].clone(), mod[:, 2].clone(), mod[:, 3].clone(), mod[:, 4].clone(), mod[:, 5].clone())
    h = _layernorm(x, axis=-1) * (1 + ca) + sa
    x = x + ga * _A_ref(h, A_k_cache, A_v_cache, A_wq, A_wo)
    h = _layernorm(x, axis=-1) * (1 + cb) + sb
    x = x + gb * _B_ref(h, B_w1, B_w2)
    return x
```

```cpp
#include <cuda_runtime.h>
#include <cuda_bf16.h>
#include <cuda.h>
#include <stdint.h>

typedef __nv_bfloat16 bf16;

namespace {

constexpr int SEQ = 2048, DM = 448, NH = 16, DH = 256, FF = 1792;
constexpr int NCTA = 128;

constexpr uint32_t OFF_QB = 0, OFF_SA = 32768, OFF_SB = 65536, OFF_RING = 98304, SLOT = 32768;
constexpr uint32_t OFF_MISC = 229376;
constexpr uint32_t OFF_FULL = OFF_MISC;
constexpr uint32_t OFF_EMPTY = OFF_MISC + 64;
constexpr uint32_t OFF_HFULL = OFF_MISC + 96;
constexpr uint32_t OFF_PFULL = OFF_MISC + 160;
constexpr uint32_t OFF_PUB = OFF_MISC + 224;
constexpr uint32_t OFF_GV = OFF_MISC + 280;
constexpr uint32_t OFF_PFG = OFF_MISC + 288;
constexpr uint32_t OFF_HS = OFF_MISC + 320;
constexpr uint32_t OFF_V0 = OFF_MISC + 336, OFF_V1 = OFF_V0 + 896, OFF_V2 = OFF_V1 + 896;
constexpr uint32_t SMEM_BYTES = OFF_MISC + 3072;
constexpr uint32_t OFF_GEMV = OFF_RING + 3 * SLOT + 16384;

__device__ __forceinline__ void wgmma_n64_rs(float (&d)[32], uint32_t a0, uint32_t a1, uint32_t a2, uint32_t a3, uint32_t bb, uint32_t bo, int scale_d) {
  asm volatile("{\n.reg .pred p;\n.reg .b32 tb;\n.reg .b64 db;\nsetp.ne.b32 p, %38, 0;\n"
    "add.u32 tb, %36, %37;\nmov.b64 db, {tb, 0x40000040};\n"
    "wgmma.mma_async.sync.aligned.m64n64k16.f32.bf16.bf16 {"
    "%0,%1,%2,%3,%4,%5,%6,%7,%8,%9,%10,%11,%12,%13,%14,%15,%16,%17,%18,%19,%20,%21,%22,%23,%24,%25,%26,%27,%28,%29,%30,%31"
    "}, {%32,%33,%34,%35}, db, p, 1, 1, 0;\n}\n"
    :
    "+f"(d[0]),"+f"(d[1]),"+f"(d[2]),"+f"(d[3]),"+f"(d[4]),"+f"(d[5]),"+f"(d[6]),"+f"(d[7]),"+f"(d[8]),"+f"(d[9]),"+f"(d[10]),"+f"(d[11]),"+f"(d[12]),
    "+f"(d[13]),"+f"(d[14]),"+f"(d[15]),"+f"(d[16]),"+f"(d[17]),"+f"(d[18]),"+f"(d[19]),"+f"(d[20]),"+f"(d[21]),"+f"(d[22]),"+f"(d[23]),"+f"(d[24]),
    "+f"(d[25]),"+f"(d[26]),"+f"(d[27]),"+f"(d[28]),"+f"(d[29]),"+f"(d[30]),"+f"(d[31])
    : "r"(a0), "r"(a1), "r"(a2), "r"(a3), "r"(bb), "r"(bo), "r"(scale_d));
}
__device__ __forceinline__ void wgmma_n64_ss(float (&d)[32], uint32_t ab, uint32_t ao, uint32_t bb, uint32_t bo, int scale_d) {
  asm volatile("{\n.reg .pred p;\n.reg .b32 ta, tb;\n.reg .b64 da, db;\nsetp.ne.b32 p, %36, 0;\n"
    "add.u32 ta, %32, %33;\nmov.b64 da, {ta, 0x40000040};\nadd.u32 tb, %34, %35;\nmov.b64 db, {tb, 0x40000040};\n"
    "wgmma.mma_async.sync.aligned.m64n64k16.f32.bf16.bf16 {"
    "%0,%1,%2,%3,%4,%5,%6,%7,%8,%9,%10,%11,%12,%13,%14,%15,%16,%17,%18,%19,%20,%21,%22,%23,%24,%25,%26,%27,%28,%29,%30,%31"
    "}, da, db, p, 1, 1, 0, 0;\n}\n"
    :
    "+f"(d[0]),"+f"(d[1]),"+f"(d[2]),"+f"(d[3]),"+f"(d[4]),"+f"(d[5]),"+f"(d[6]),"+f"(d[7]),"+f"(d[8]),"+f"(d[9]),"+f"(d[10]),"+f"(d[11]),"+f"(d[12]),
    "+f"(d[13]),"+f"(d[14]),"+f"(d[15]),"+f"(d[16]),"+f"(d[17]),"+f"(d[18]),"+f"(d[19]),"+f"(d[20]),"+f"(d[21]),"+f"(d[22]),"+f"(d[23]),"+f"(d[24]),
    "+f"(d[25]),"+f"(d[26]),"+f"(d[27]),"+f"(d[28]),"+f"(d[29]),"+f"(d[30]),"+f"(d[31])
    : "r"(ab), "r"(ao), "r"(bb), "r"(bo), "r"(scale_d));
}
__device__ __forceinline__ void wgmma_n256_rs_tb(float (&d)[128], uint32_t a0, uint32_t a1, uint32_t a2, uint32_t a3, uint32_t bb, uint32_t bo, int scale_d) {
  asm volatile("{\n.reg .pred p;\n.reg .b32 tb;\n.reg .b64 db;\nsetp.ne.b32 p, %134, 0;\n"
    "add.u32 tb, %132, %133;\nmov.b64 db, {tb, 0x40000040};\n"
    "wgmma.mma_async.sync.aligned.m64n256k16.f32.bf16.bf16 {"
    "%0,%1,%2,%3,%4,%5,%6,%7,%8,%9,%10,%11,%12,%13,%14,%15,%16,%17,%18,%19,%20,%21,%22,%23,%24,%25,%26,%27,%28,%29,%30,%31,%32,%33,%34,%35,%36,%37,%38,%39,"
    "%40,%41,%42,%43,%44,%45,%46,%47,%48,%49,%50,%51,%52,%53,%54,%55,%56,%57,%58,%59,%60,%61,%62,%63,%64,%65,%66,%67,%68,%69,%70,%71,%72,%73,%74,%75,%76,"
    "%77,%78,%79,%80,%81,%82,%83,%84,%85,%86,%87,%88,%89,%90,%91,%92,%93,%94,%95,%96,%97,%98,%99,%100,%101,%102,%103,%104,%105,%106,%107,%108,%109,%110,"
    "%111,%112,%113,%114,%115,%116,%117,%118,%119,%120,%121,%122,%123,%124,%125,%126,%127"
    "}, {%128,%129,%130,%131}, db, p, 1, 1, 1;\n}\n"
    :
    "+f"(d[0]),"+f"(d[1]),"+f"(d[2]),"+f"(d[3]),"+f"(d[4]),"+f"(d[5]),"+f"(d[6]),"+f"(d[7]),"+f"(d[8]),"+f"(d[9]),"+f"(d[10]),"+f"(d[11]),"+f"(d[12]),
    "+f"(d[13]),"+f"(d[14]),"+f"(d[15]),"+f"(d[16]),"+f"(d[17]),"+f"(d[18]),"+f"(d[19]),"+f"(d[20]),"+f"(d[21]),"+f"(d[22]),"+f"(d[23]),"+f"(d[24]),
    "+f"(d[25]),"+f"(d[26]),"+f"(d[27]),"+f"(d[28]),"+f"(d[29]),"+f"(d[30]),"+f"(d[31]),"+f"(d[32]),"+f"(d[33]),"+f"(d[34]),"+f"(d[35]),"+f"(d[36]),
    "+f"(d[37]),"+f"(d[38]),"+f"(d[39]),"+f"(d[40]),"+f"(d[41]),"+f"(d[42]),"+f"(d[43]),"+f"(d[44]),"+f"(d[45]),"+f"(d[46]),"+f"(d[47]),"+f"(d[48]),
    "+f"(d[49]),"+f"(d[50]),"+f"(d[51]),"+f"(d[52]),"+f"(d[53]),"+f"(d[54]),"+f"(d[55]),"+f"(d[56]),"+f"(d[57]),"+f"(d[58]),"+f"(d[59]),"+f"(d[60]),
    "+f"(d[61]),"+f"(d[62]),"+f"(d[63]),"+f"(d[64]),"+f"(d[65]),"+f"(d[66]),"+f"(d[67]),"+f"(d[68]),"+f"(d[69]),"+f"(d[70]),"+f"(d[71]),"+f"(d[72]),
    "+f"(d[73]),"+f"(d[74]),"+f"(d[75]),"+f"(d[76]),"+f"(d[77]),"+f"(d[78]),"+f"(d[79]),"+f"(d[80]),"+f"(d[81]),"+f"(d[82]),"+f"(d[83]),"+f"(d[84]),
    "+f"(d[85]),"+f"(d[86]),"+f"(d[87]),"+f"(d[88]),"+f"(d[89]),"+f"(d[90]),"+f"(d[91]),"+f"(d[92]),"+f"(d[93]),"+f"(d[94]),"+f"(d[95]),"+f"(d[96]),
    "+f"(d[97]),"+f"(d[98]),"+f"(d[99]),"+f"(d[100]),"+f"(d[101]),"+f"(d[102]),"+f"(d[103]),"+f"(d[104]),"+f"(d[105]),"+f"(d[106]),"+f"(d[107]),
    "+f"(d[108]),"+f"(d[109]),"+f"(d[110]),"+f"(d[111]),"+f"(d[112]),"+f"(d[113]),"+f"(d[114]),"+f"(d[115]),"+f"(d[116]),"+f"(d[117]),"+f"(d[118]),
    "+f"(d[119]),"+f"(d[120]),"+f"(d[121]),"+f"(d[122]),"+f"(d[123]),"+f"(d[124]),"+f"(d[125]),"+f"(d[126]),"+f"(d[127])
    : "r"(a0), "r"(a1), "r"(a2), "r"(a3), "r"(bb), "r"(bo), "r"(scale_d));
}
__device__ __forceinline__ void wgmma_n256_ss_tb(float (&d)[128], uint32_t ab, uint32_t ao, uint32_t bb, uint32_t bo, int scale_d) {
  asm volatile("{\n.reg .pred p;\n.reg .b32 ta, tb;\n.reg .b64 da, db;\nsetp.ne.b32 p, %132, 0;\n"
    "add.u32 ta, %128, %129;\nmov.b64 da, {ta, 0x40000040};\nadd.u32 tb, %130, %131;\nmov.b64 db, {tb, 0x40000040};\n"
    "wgmma.mma_async.sync.aligned.m64n256k16.f32.bf16.bf16 {"
    "%0,%1,%2,%3,%4,%5,%6,%7,%8,%9,%10,%11,%12,%13,%14,%15,%16,%17,%18,%19,%20,%21,%22,%23,%24,%25,%26,%27,%28,%29,%30,%31,%32,%33,%34,%35,%36,%37,%38,%39,"
    "%40,%41,%42,%43,%44,%45,%46,%47,%48,%49,%50,%51,%52,%53,%54,%55,%56,%57,%58,%59,%60,%61,%62,%63,%64,%65,%66,%67,%68,%69,%70,%71,%72,%73,%74,%75,%76,"
    "%77,%78,%79,%80,%81,%82,%83,%84,%85,%86,%87,%88,%89,%90,%91,%92,%93,%94,%95,%96,%97,%98,%99,%100,%101,%102,%103,%104,%105,%106,%107,%108,%109,%110,"
    "%111,%112,%113,%114,%115,%116,%117,%118,%119,%120,%121,%122,%123,%124,%125,%126,%127"
    "}, da, db, p, 1, 1, 0, 1;\n}\n"
    :
    "+f"(d[0]),"+f"(d[1]),"+f"(d[2]),"+f"(d[3]),"+f"(d[4]),"+f"(d[5]),"+f"(d[6]),"+f"(d[7]),"+f"(d[8]),"+f"(d[9]),"+f"(d[10]),"+f"(d[11]),"+f"(d[12]),
    "+f"(d[13]),"+f"(d[14]),"+f"(d[15]),"+f"(d[16]),"+f"(d[17]),"+f"(d[18]),"+f"(d[19]),"+f"(d[20]),"+f"(d[21]),"+f"(d[22]),"+f"(d[23]),"+f"(d[24]),
    "+f"(d[25]),"+f"(d[26]),"+f"(d[27]),"+f"(d[28]),"+f"(d[29]),"+f"(d[30]),"+f"(d[31]),"+f"(d[32]),"+f"(d[33]),"+f"(d[34]),"+f"(d[35]),"+f"(d[36]),
    "+f"(d[37]),"+f"(d[38]),"+f"(d[39]),"+f"(d[40]),"+f"(d[41]),"+f"(d[42]),"+f"(d[43]),"+f"(d[44]),"+f"(d[45]),"+f"(d[46]),"+f"(d[47]),"+f"(d[48]),
    "+f"(d[49]),"+f"(d[50]),"+f"(d[51]),"+f"(d[52]),"+f"(d[53]),"+f"(d[54]),"+f"(d[55]),"+f"(d[56]),"+f"(d[57]),"+f"(d[58]),"+f"(d[59]),"+f"(d[60]),
    "+f"(d[61]),"+f"(d[62]),"+f"(d[63]),"+f"(d[64]),"+f"(d[65]),"+f"(d[66]),"+f"(d[67]),"+f"(d[68]),"+f"(d[69]),"+f"(d[70]),"+f"(d[71]),"+f"(d[72]),
    "+f"(d[73]),"+f"(d[74]),"+f"(d[75]),"+f"(d[76]),"+f"(d[77]),"+f"(d[78]),"+f"(d[79]),"+f"(d[80]),"+f"(d[81]),"+f"(d[82]),"+f"(d[83]),"+f"(d[84]),
    "+f"(d[85]),"+f"(d[86]),"+f"(d[87]),"+f"(d[88]),"+f"(d[89]),"+f"(d[90]),"+f"(d[91]),"+f"(d[92]),"+f"(d[93]),"+f"(d[94]),"+f"(d[95]),"+f"(d[96]),
    "+f"(d[97]),"+f"(d[98]),"+f"(d[99]),"+f"(d[100]),"+f"(d[101]),"+f"(d[102]),"+f"(d[103]),"+f"(d[104]),"+f"(d[105]),"+f"(d[106]),"+f"(d[107]),
    "+f"(d[108]),"+f"(d[109]),"+f"(d[110]),"+f"(d[111]),"+f"(d[112]),"+f"(d[113]),"+f"(d[114]),"+f"(d[115]),"+f"(d[116]),"+f"(d[117]),"+f"(d[118]),
    "+f"(d[119]),"+f"(d[120]),"+f"(d[121]),"+f"(d[122]),"+f"(d[123]),"+f"(d[124]),"+f"(d[125]),"+f"(d[126]),"+f"(d[127])
    : "r"(ab), "r"(ao), "r"(bb), "r"(bo), "r"(scale_d));
}
__device__ __forceinline__ void wgmma_n64_rs_tb(float (&d)[32], uint32_t a0, uint32_t a1, uint32_t a2, uint32_t a3, uint32_t bb, uint32_t bo, int scale_d) {
  asm volatile("{\n.reg .pred p;\n.reg .b32 tb;\n.reg .b64 db;\nsetp.ne.b32 p, %38, 0;\n"
    "add.u32 tb, %36, %37;\nmov.b64 db, {tb, 0x40000040};\n"
    "wgmma.mma_async.sync.aligned.m64n64k16.f32.bf16.bf16 {"
    "%0,%1,%2,%3,%4,%5,%6,%7,%8,%9,%10,%11,%12,%13,%14,%15,%16,%17,%18,%19,%20,%21,%22,%23,%24,%25,%26,%27,%28,%29,%30,%31"
    "}, {%32,%33,%34,%35}, db, p, 1, 1, 1;\n}\n"
    :
    "+f"(d[0]),"+f"(d[1]),"+f"(d[2]),"+f"(d[3]),"+f"(d[4]),"+f"(d[5]),"+f"(d[6]),"+f"(d[7]),"+f"(d[8]),"+f"(d[9]),"+f"(d[10]),"+f"(d[11]),"+f"(d[12]),
    "+f"(d[13]),"+f"(d[14]),"+f"(d[15]),"+f"(d[16]),"+f"(d[17]),"+f"(d[18]),"+f"(d[19]),"+f"(d[20]),"+f"(d[21]),"+f"(d[22]),"+f"(d[23]),"+f"(d[24]),
    "+f"(d[25]),"+f"(d[26]),"+f"(d[27]),"+f"(d[28]),"+f"(d[29]),"+f"(d[30]),"+f"(d[31])
    : "r"(a0), "r"(a1), "r"(a2), "r"(a3), "r"(bb), "r"(bo), "r"(scale_d));
}
__device__ __forceinline__ void wgmma_n64_ss_tb(float (&d)[32], uint32_t ab, uint32_t ao, uint32_t bb, uint32_t bo, int scale_d) {
  asm volatile("{\n.reg .pred p;\n.reg .b32 ta, tb;\n.reg .b64 da, db;\nsetp.ne.b32 p, %36, 0;\n"
    "add.u32 ta, %32, %33;\nmov.b64 da, {ta, 0x40000040};\nadd.u32 tb, %34, %35;\nmov.b64 db, {tb, 0x40000040};\n"
    "wgmma.mma_async.sync.aligned.m64n64k16.f32.bf16.bf16 {"
    "%0,%1,%2,%3,%4,%5,%6,%7,%8,%9,%10,%11,%12,%13,%14,%15,%16,%17,%18,%19,%20,%21,%22,%23,%24,%25,%26,%27,%28,%29,%30,%31"
    "}, da, db, p, 1, 1, 0, 1;\n}\n"
    :
    "+f"(d[0]),"+f"(d[1]),"+f"(d[2]),"+f"(d[3]),"+f"(d[4]),"+f"(d[5]),"+f"(d[6]),"+f"(d[7]),"+f"(d[8]),"+f"(d[9]),"+f"(d[10]),"+f"(d[11]),"+f"(d[12]),
    "+f"(d[13]),"+f"(d[14]),"+f"(d[15]),"+f"(d[16]),"+f"(d[17]),"+f"(d[18]),"+f"(d[19]),"+f"(d[20]),"+f"(d[21]),"+f"(d[22]),"+f"(d[23]),"+f"(d[24]),
    "+f"(d[25]),"+f"(d[26]),"+f"(d[27]),"+f"(d[28]),"+f"(d[29]),"+f"(d[30]),"+f"(d[31])
    : "r"(ab), "r"(ao), "r"(bb), "r"(bo), "r"(scale_d));
}
__device__ __forceinline__ void wgmma_n224_ss_tb(float (&d)[112], uint32_t ab, uint32_t ao, uint32_t bb, uint32_t bo, int scale_d) {
  asm volatile("{\n.reg .pred p;\n.reg .b32 ta, tb;\n.reg .b64 da, db;\nsetp.ne.b32 p, %116, 0;\n"
    "add.u32 ta, %112, %113;\nmov.b64 da, {ta, 0x40000040};\nadd.u32 tb, %114, %115;\nmov.b64 db, {tb, 0x40000040};\n"
    "wgmma.mma_async.sync.aligned.m64n224k16.f32.bf16.bf16 {"
    "%0,%1,%2,%3,%4,%5,%6,%7,%8,%9,%10,%11,%12,%13,%14,%15,%16,%17,%18,%19,%20,%21,%22,%23,%24,%25,%26,%27,%28,%29,%30,%31,%32,%33,%34,%35,%36,%37,%38,%39,"
    "%40,%41,%42,%43,%44,%45,%46,%47,%48,%49,%50,%51,%52,%53,%54,%55,%56,%57,%58,%59,%60,%61,%62,%63,%64,%65,%66,%67,%68,%69,%70,%71,%72,%73,%74,%75,%76,"
    "%77,%78,%79,%80,%81,%82,%83,%84,%85,%86,%87,%88,%89,%90,%91,%92,%93,%94,%95,%96,%97,%98,%99,%100,%101,%102,%103,%104,%105,%106,%107,%108,%109,%110,"
    "%111"
    "}, da, db, p, 1, 1, 0, 1;\n}\n"
    :
    "+f"(d[0]),"+f"(d[1]),"+f"(d[2]),"+f"(d[3]),"+f"(d[4]),"+f"(d[5]),"+f"(d[6]),"+f"(d[7]),"+f"(d[8]),"+f"(d[9]),"+f"(d[10]),"+f"(d[11]),"+f"(d[12]),
    "+f"(d[13]),"+f"(d[14]),"+f"(d[15]),"+f"(d[16]),"+f"(d[17]),"+f"(d[18]),"+f"(d[19]),"+f"(d[20]),"+f"(d[21]),"+f"(d[22]),"+f"(d[23]),"+f"(d[24]),
    "+f"(d[25]),"+f"(d[26]),"+f"(d[27]),"+f"(d[28]),"+f"(d[29]),"+f"(d[30]),"+f"(d[31]),"+f"(d[32]),"+f"(d[33]),"+f"(d[34]),"+f"(d[35]),"+f"(d[36]),
    "+f"(d[37]),"+f"(d[38]),"+f"(d[39]),"+f"(d[40]),"+f"(d[41]),"+f"(d[42]),"+f"(d[43]),"+f"(d[44]),"+f"(d[45]),"+f"(d[46]),"+f"(d[47]),"+f"(d[48]),
    "+f"(d[49]),"+f"(d[50]),"+f"(d[51]),"+f"(d[52]),"+f"(d[53]),"+f"(d[54]),"+f"(d[55]),"+f"(d[56]),"+f"(d[57]),"+f"(d[58]),"+f"(d[59]),"+f"(d[60]),
    "+f"(d[61]),"+f"(d[62]),"+f"(d[63]),"+f"(d[64]),"+f"(d[65]),"+f"(d[66]),"+f"(d[67]),"+f"(d[68]),"+f"(d[69]),"+f"(d[70]),"+f"(d[71]),"+f"(d[72]),
    "+f"(d[73]),"+f"(d[74]),"+f"(d[75]),"+f"(d[76]),"+f"(d[77]),"+f"(d[78]),"+f"(d[79]),"+f"(d[80]),"+f"(d[81]),"+f"(d[82]),"+f"(d[83]),"+f"(d[84]),
    "+f"(d[85]),"+f"(d[86]),"+f"(d[87]),"+f"(d[88]),"+f"(d[89]),"+f"(d[90]),"+f"(d[91]),"+f"(d[92]),"+f"(d[93]),"+f"(d[94]),"+f"(d[95]),"+f"(d[96]),
    "+f"(d[97]),"+f"(d[98]),"+f"(d[99]),"+f"(d[100]),"+f"(d[101]),"+f"(d[102]),"+f"(d[103]),"+f"(d[104]),"+f"(d[105]),"+f"(d[106]),"+f"(d[107]),
    "+f"(d[108]),"+f"(d[109]),"+f"(d[110]),"+f"(d[111])
    : "r"(ab), "r"(ao), "r"(bb), "r"(bo), "r"(scale_d));
}


__device__ uint2 g_mod[6 * DM];
__device__ __align__(1024) uint4 g_part[(size_t)NCTA * 8 * 7 * 4 * 32];
__device__ __align__(1024) bf16 g_h2[(size_t)SEQ * DM];
__device__ __align__(1024) float g_x1[(size_t)NCTA * 7 * 256 * 4];
__device__ __align__(256) unsigned g_flag[2 * 16 * 8 * 8 + 16 * 8];
__device__ unsigned g_epoch[NCTA];

__device__ __forceinline__ uint32_t dlo(uint32_t saddr, uint32_t lbo) { return ((saddr & 0x3FFFF) >> 4) + ((lbo >> 4) << 16); }
__device__ __forceinline__ void wg_fence() { asm volatile("wgmma.fence.sync.aligned;\n" ::: "memory"); }
__device__ __forceinline__ void wg_commit() { asm volatile("wgmma.commit_group.sync.aligned;\n" ::: "memory"); }
template <int N> __device__ __forceinline__ void wg_wait() { asm volatile("wgmma.wait_group.sync.aligned %0;\n" ::"n"(N) : "memory"); }
template <int N> __device__ __forceinline__ void fence_regs(float (&r)[N]) {
#pragma unroll
  for (int i = 0; i < N; i++) asm volatile("" : "+f"(r[i])::"memory");
}
template <int N> __device__ __forceinline__ void fence_regs(uint32_t (&r)[N]) {
#pragma unroll
  for (int i = 0; i < N; i++) asm volatile("" : "+r"(r[i])::"memory");
}
__device__ __forceinline__ void mbar_init(uint32_t a, uint32_t cnt) { asm volatile("mbarrier.init.shared::cta.b64 [%0], %1;" ::"r"(a), "r"(cnt) : "memory"); }
__device__ __forceinline__ void mbar_expect_tx(uint32_t a, uint32_t bytes) { asm volatile("mbarrier.arrive.expect_tx.shared::cta.b64 _, [%0], %1;" ::"r"(a), "r"(bytes) : "memory"); }
__device__ __forceinline__ void mbar_arrive(uint32_t a) { asm volatile("mbarrier.arrive.shared::cta.b64 _, [%0];" ::"r"(a) : "memory"); }
__device__ __forceinline__ void mbar_arrive_remote(uint32_t a, uint32_t cta) {
  asm volatile("{\n.reg .b32 ra;\nmapa.shared::cluster.u32 ra, %0, %1;\nmbarrier.arrive.shared::cluster.b64 _, [ra];\n}" ::"r"(a), "r"(cta) : "memory");
}
__device__ __forceinline__ void mbar_wait(uint32_t a, uint32_t parity) {
  asm volatile(
      "{\n.reg .pred p;\n.reg .u32 c;\nmov.u32 c, 0;\nWAIT_%=:\nmbarrier.try_wait.parity.shared::cta.b64 p, [%0], %1;\n@p bra DONE_%=;\n"
      "add.u32 c, c, 1;\nsetp.gt.u32 p, c, 16777216;\n@p trap;\nbra WAIT_%=;\nDONE_%=:\n}" ::"r"(a), "r"(parity) : "memory");
}
__device__ __forceinline__ int grp_first(int ex, int q) { return ex == 0 ? (q == 0 ? 0 : (q == 1 ? 2 : 5)) : 2 * q; }
__device__ __forceinline__ int grp_size(int ex, int q) { return ex == 0 ? (q == 1 ? 3 : 2) : (q < 3 ? 2 : 1); }
__device__ __forceinline__ int grp_of(int ex, int p) { return ex == 0 ? (p < 2 ? 0 : (p < 5 ? 1 : 2)) : p >> 1; }
__device__ __forceinline__ uint32_t grp_base(int ex, int q) {
  if (ex == 0) return q == 0 ? OFF_SB : (q == 1 ? OFF_QB : OFF_RING + 3 * SLOT);
  return q == 0 ? OFF_RING + SLOT : (q == 1 ? OFF_RING : (q == 2 ? OFF_QB : OFF_SB));
}
__device__ __forceinline__ void tma_load3(uint32_t dst, const CUtensorMap* tm, uint32_t bar, int c0, int c1, int c2) {
  asm volatile("cp.async.bulk.tensor.3d.shared::cluster.global.mbarrier::complete_tx::bytes.multicast::cluster [%0], [%1, {%3, %4, %5}], [%2], %6;"
               ::"r"(dst), "l"(tm), "r"(bar), "r"(c0), "r"(c1), "r"(c2), "h"((uint16_t)3) : "memory");
}
__device__ __forceinline__ void tma_load2(uint32_t dst, const CUtensorMap* tm, uint32_t bar, int c0, int c1) {
  asm volatile("cp.async.bulk.tensor.2d.shared::cluster.global.mbarrier::complete_tx::bytes.multicast::cluster [%0], [%1, {%3, %4}], [%2], %5;"
               ::"r"(dst), "l"(tm), "r"(bar), "r"(c0), "r"(c1), "h"((uint16_t)3) : "memory");
}
__device__ __forceinline__ void tma_load3_local(uint32_t dst, const CUtensorMap* tm, uint32_t bar, int c0, int c1, int c2) {
  asm volatile("cp.async.bulk.tensor.3d.shared::cluster.global.mbarrier::complete_tx::bytes [%0], [%1, {%3, %4, %5}], [%2];"
               ::"r"(dst), "l"(tm), "r"(bar), "r"(c0), "r"(c1), "r"(c2) : "memory");
}
__device__ __forceinline__ void tma_prefetch3(const CUtensorMap* tm, int c0, int c1, int c2) {
  asm volatile("cp.async.bulk.prefetch.tensor.3d.L2.global.tile [%0, {%1, %2, %3}];" ::"l"(tm), "r"(c0), "r"(c1), "r"(c2) : "memory");
}
__device__ __forceinline__ void bulk_load(uint32_t dst, const void* src, uint32_t bytes, uint32_t bar) {
  asm volatile("cp.async.bulk.shared::cluster.global.mbarrier::complete_tx::bytes [%0], [%1], %2, [%3];" ::"r"(dst), "l"(src), "r"(bytes), "r"(bar) : "memory");
}
__device__ __forceinline__ void bulk_store(void* dst, uint32_t src, uint32_t bytes) {
  asm volatile("cp.async.bulk.global.shared::cta.bulk_group [%0], [%1], %2;" ::"l"(dst), "r"(src), "r"(bytes) : "memory");
  asm volatile("cp.async.bulk.commit_group;" ::: "memory");
}
template <int N> __device__ __forceinline__ void bulk_wait() { asm volatile("cp.async.bulk.wait_group %0;" ::"n"(N) : "memory"); }
__device__ __forceinline__ void fence_async_smem() { asm volatile("fence.proxy.async.shared::cta;" ::: "memory"); }
__device__ __forceinline__ float ex2(float x) { float y; asm("ex2.approx.ftz.f32 %0, %1;" : "=f"(y) : "f"(x)); return y; }
__device__ __forceinline__ float tanh_fast(float x) { float y; asm("tanh.approx.f32 %0, %1;" : "=f"(y) : "f"(x)); return y; }
__device__ __forceinline__ uint32_t pack_bf16(float lo, float hi) { uint32_t r; asm("cvt.rn.bf16x2.f32 %0, %1, %2;" : "=r"(r) : "f"(hi), "f"(lo)); return r; }
__device__ __forceinline__ float bf_lo(uint32_t v) { return __uint_as_float(v << 16); }
__device__ __forceinline__ float bf_hi(uint32_t v) { return __uint_as_float(v & 0xffff0000u); }
__device__ __forceinline__ float round_bf16(float x) { return __bfloat162float(__float2bfloat16_rn(x)); }
__device__ __forceinline__ uint32_t hfma2_bf16(uint32_t a, uint32_t b, uint32_t c) { uint32_t r; asm("fma.rn.bf16x2 %0, %1, %2, %3;" : "=r"(r) : "r"(a), "r"(b), "r"(c)); return r; }
__device__ __forceinline__ void named_sync(int id, int n) { asm volatile("bar.sync %0, %1;" ::"r"(id), "r"(n) : "memory"); }
__device__ __forceinline__ void named_arrive(int id, int n) { asm volatile("bar.arrive %0, %1;" ::"r"(id), "r"(n) : "memory"); }
__device__ __forceinline__ void cluster_arrive() { asm volatile("barrier.cluster.arrive.relaxed.aligned;" ::: "memory"); }
__device__ __forceinline__ void cluster_wait() { asm volatile("barrier.cluster.wait.aligned;" ::: "memory"); }
__device__ __forceinline__ void stsm4(uint32_t addr, uint32_t r0, uint32_t r1, uint32_t r2, uint32_t r3) {
  asm volatile("stmatrix.sync.aligned.m8n8.x4.shared.b16 [%0], {%1, %2, %3, %4};" ::"r"(addr), "r"(r0), "r"(r1), "r"(r2), "r"(r3) : "memory");
}
__device__ __forceinline__ void ldsm4(uint32_t addr, uint32_t& r0, uint32_t& r1, uint32_t& r2, uint32_t& r3) {
  asm volatile("ldmatrix.sync.aligned.m8n8.x4.shared.b16 {%0, %1, %2, %3}, [%4];" : "=r"(r0), "=r"(r1), "=r"(r2), "=r"(r3) : "r"(addr) : "memory");
}
__device__ __forceinline__ void mma16816(float (&d)[4], uint32_t a0, uint32_t a1, uint32_t a2, uint32_t a3, uint32_t b0, uint32_t b1) {
  asm volatile("mma.sync.aligned.m16n8k16.row.col.f32.bf16.bf16.f32 {%0, %1, %2, %3}, {%4, %5, %6, %7}, {%8, %9}, {%0, %1, %2, %3};"
               : "+f"(d[0]), "+f"(d[1]), "+f"(d[2]), "+f"(d[3]) : "r"(a0), "r"(a1), "r"(a2), "r"(a3), "r"(b0), "r"(b1));
}
__device__ __forceinline__ uint4 ldg_nc(const void* p) {
  uint4 v; asm volatile("ld.global.nc.v4.u32 {%0, %1, %2, %3}, [%4];" : "=r"(v.x), "=r"(v.y), "=r"(v.z), "=r"(v.w) : "l"(p)); return v;
}
__device__ __forceinline__ uint4 lds128(uint32_t a) {
  uint4 v; asm volatile("ld.shared.v4.u32 {%0, %1, %2, %3}, [%4];" : "=r"(v.x), "=r"(v.y), "=r"(v.z), "=r"(v.w) : "r"(a) : "memory"); return v;
}
__device__ __forceinline__ void wait_flags8(const unsigned* p, int own, unsigned tag) {
  uint32_t spins = 0;
  bool ok;
  do {
    uint4 a, c;
    asm volatile("ld.relaxed.gpu.global.v4.u32 {%0, %1, %2, %3}, [%4];" : "=r"(a.x), "=r"(a.y), "=r"(a.z), "=r"(a.w) : "l"(p) : "memory");
    asm volatile("ld.relaxed.gpu.global.v4.u32 {%0, %1, %2, %3}, [%4];" : "=r"(c.x), "=r"(c.y), "=r"(c.z), "=r"(c.w) : "l"(p + 4) : "memory");
    ok = (a.x == tag || own == 0) && (a.y == tag || own == 1) && (a.z == tag || own == 2) && (a.w == tag || own == 3) &&
         (c.x == tag || own == 4) && (c.y == tag || own == 5) && (c.z == tag || own == 6) && (c.w == tag || own == 7);
  } while (!ok && ++spins < (1u << 24));
}
__device__ __forceinline__ float2 load_mod_pair(int n, unsigned tag) {
  uint32_t x, y;
  asm volatile(
      "{\n.reg .pred p, q;\n.reg .u32 c, t0, t1;\nmov.u32 c, 0;\nWAIT_%=:\nld.volatile.global.v4.u32 {%0, t0, %1, t1}, [%2];\n"
      "setp.eq.u32 p, t0, %3;\nsetp.eq.and.u32 p, t1, %3, p;\n@p bra DONE_%=;\n"
      "nanosleep.u32 64;\nadd.u32 c, c, 1;\nsetp.gt.u32 q, c, 4194304;\n@q trap;\nbra WAIT_%=;\nDONE_%=:\n}"
      : "=&r"(x), "=&r"(y) : "l"(&g_mod[n]), "r"(tag) : "memory");
  return make_float2(__uint_as_float(x), __uint_as_float(y));
}

struct Params {
  const bf16* x; const bf16* c; const bf16* wmod; bf16* out;
};

constexpr int XWAIT = 4;
constexpr int GVCRIT = 28;
constexpr int PFD = 8;
__device__ __forceinline__ unsigned* flag_part(int ex, int g, int p) { return g_flag + ((ex * 16 + g) * 8 + p) * 8; }
__device__ __forceinline__ unsigned* flag_h2(int g) { return g_flag + 2 * 16 * 8 * 8 + g * 8; }
__device__ __forceinline__ void st_flag(unsigned* p, unsigned v) { asm volatile("red.relaxed.gpu.global.max.u32 [%0], %1;" ::"l"(p), "r"(v) : "memory"); }
constexpr float SL2 = 0.0625f * 1.4426950408889634f;
constexpr float TAU = 8.0f / SL2;

__global__ void __launch_bounds__(384, 1)
fused_kernel(const __grid_constant__ CUtensorMap tmK, const __grid_constant__ CUtensorMap tmV,
             const __grid_constant__ CUtensorMap tmWq, const __grid_constant__ CUtensorMap tmWo,
             const __grid_constant__ CUtensorMap tmW1, const __grid_constant__ CUtensorMap tmW2,
             const __grid_constant__ CUtensorMap tmX, const __grid_constant__ CUtensorMap tmH2,
             const Params prm) {
  extern __shared__ __align__(1024) uint8_t smem_raw[];
  const uint32_t sb = (uint32_t)__cvta_generic_to_shared(smem_raw);
  const int warp = __shfl_sync(0xffffffff, (int)(threadIdx.x >> 5), 0);
  const int lane = threadIdx.x & 31;
  const int b = blockIdx.x;
  const int rank = b & 1;
  const int j = (b >> 1) & 7;
  const int g = ((b >> 4) << 1) | rank;
  constexpr uint32_t EMPTY_CNT = 16;
  const uint32_t ring = sb + OFF_RING, full = sb + OFF_FULL, empty = sb + OFF_EMPTY;

  uint4 wv[7]; bf16 cv[7];
  if (warp < 8 && b < 84) {
#pragma unroll
    for (int i = 0; i < 7; i++) {
      const int r = (threadIdx.x >> 2) + 64 * i;
      wv[i] = ldg_nc(prm.wmod + (size_t)r * (6 * DM) + b * 32 + (threadIdx.x & 3) * 8);
      cv[i] = prm.c[r];
    }
  }
  auto load_tile = [&](const CUtensorMap* tm) {
#pragma unroll 1
    for (int q = 0; q < 7; q++) {
      mbar_expect_tx(sb + OFF_HFULL + 8 * q, 16384);
      tma_load3_local(q < 6 ? sb + q * 16384 : ring + 3 * SLOT, tm, sb + OFF_HFULL + 8 * q, 0, g * 128, q);
    }
  };
  if (threadIdx.x == 256) {
    for (int i = 0; i < 7; i++) mbar_init(full + 8 * i, 1);
    for (int i = 0; i < 4; i++) mbar_init(empty + 8 * i, EMPTY_CNT);
    for (int i = 0; i < 7; i++) mbar_init(sb + OFF_HFULL + 8 * i, 1);
    for (int i = 0; i < 7; i++) { mbar_init(sb + OFF_PFULL + 8 * i, 1); mbar_init(sb + OFF_PUB + 8 * i, 8); }
    mbar_init(sb + OFF_GV, 8);
    for (int i = 0; i < 4; i++) mbar_init(sb + OFF_PFG + 8 * i, 1);
    mbar_init(sb + OFF_HS, 16);
    asm volatile("fence.mbarrier_init.release.cluster;" ::: "memory");
    fence_async_smem();
    if (b >= GVCRIT) load_tile(&tmX);
  }
  __syncthreads();
  cluster_arrive();

  if (warp >= 8) {
    asm volatile("setmaxnreg.dec.sync.aligned.u32 24;");
    if (b < GVCRIT && warp == 8 && lane == 0) { mbar_wait(sb + OFF_GV, 0); load_tile(&tmX); }
    cluster_wait();
    if (warp == 8 && lane == 0) {
      const unsigned tag = g_epoch[b] + 1;
      uint32_t pmask = 8;
      auto acquire = [&](int s, uint32_t bytes) {
        mbar_wait(empty + 8 * s, ((pmask >> s) & 1) ^ 1);
        pmask ^= 1u << s;
        if (bytes) mbar_expect_tx(full + 8 * s, bytes);
      };
      auto load_pair3 = [&](int s, uint32_t half, const CUtensorMap* tm, int r0, int c0, int r1, int c1) {
        tma_load3(ring + s * SLOT + rank * half, tm, full + 8 * s, 0, rank ? r1 : r0, rank ? c1 : c0);
      };
      auto load_pair2 = [&](uint32_t dst, uint32_t half, int s, const CUtensorMap* tm, int col, int row) {
        tma_load2(dst + rank * half, tm, full + 8 * s, col + rank * 64, row);
      };
      auto load_rows2 = [&](uint32_t dst, uint32_t half, int s, const CUtensorMap* tm, int col, int row, int rows) {
        tma_load2(dst + rank * half, tm, full + 8 * s, col, row + rank * rows);
      };
      mbar_wait(sb + OFF_HFULL + 8 * XWAIT, 0);
#pragma unroll 1
      for (int i = 0; i < 14; i++) {
        const int s = i % 3, kc = i % 7, head = 2 * j + (i < 7 ? 1 : 0);
        acquire(s, SLOT);
        load_pair3(s, 16384, &tmWq, kc * 64, head * 4, kc * 64, head * 4 + 2);
      }
#pragma unroll 1
      for (int u = 0; u < 128; u++) {
        const int s = (u + 2) & 3;
        const int row = (2 * j + (u >> 6)) * SEQ + ((u >> 1) & 31) * 64;
        if (u + PFD < 128 && (((u + PFD) >> 1) & 7) == (b >> 4)) {
          const int up = u + PFD;
          tma_prefetch3((up & 1) ? &tmV : &tmK, 0, (2 * j + (up >> 6)) * SEQ + ((up >> 1) & 31) * 64, rank * 2);
        }
        acquire(s, SLOT);
        load_pair3(s, 16384, (u & 1) ? &tmV : &tmK, row, 0, row, 2);
      }
#pragma unroll 1
      for (int u = 0; u < 14; u++) {
        const int s = (u + 2) & 3;
        acquire(s, SLOT);
        load_rows2(ring + s * SLOT, 16384, s, &tmWo, (u >> 1) * 64, 2 * j * DH + (u & 1) * 256, 128);
      }
#pragma unroll 1
      for (int i = 0; i < 7; i++) {
        const int s = i % 3;
        if (i == 3) {
          acquire(3, 0);
          mbar_wait(sb + OFF_HS, 0);
          wait_flags8(flag_h2(g), j, tag * 16);
          asm volatile("fence.acquire.gpu;" ::: "memory");
          asm volatile("fence.proxy.async.global;" ::: "memory");
          load_tile(&tmH2);
        }
        acquire(s, SLOT);
        load_pair2(ring + s * SLOT, 8192, s, &tmW1, j * 224, i * 64);
        load_pair2(ring + s * SLOT + 16384, 8192, s, &tmW1, j * 224 + 128, i * 64);
      }
#pragma unroll 1
      for (int v = 0; v < 7; v++) {
        const int s = v < 2 ? v + 1 : (v == 2 ? 0 : v);
        if (v < 4) acquire(s, 28672); else mbar_expect_tx(full + 8 * s, 28672);
        load_rows2(s < 4 ? ring + s * SLOT : sb + (s - 4) * SLOT, 14336, s, &tmW2, v * 64, j * 224, 112);
      }
    }
    if (warp > 8) {
      const unsigned tag = g_epoch[b] + 1;
      named_sync(7, 352);
#pragma unroll 1
      for (int n = (threadIdx.x - 288) * 2; n < 3 * DM; n += 192) {
        const float2 v = load_mod_pair(2 * DM + n, tag);
        const float one = n >= 2 * DM ? 1.f : 0.f;
        *reinterpret_cast<uint32_t*>(smem_raw + OFF_V0 + n * 2) = pack_bf16(one + v.x, one + v.y);
      }
      named_arrive(8, 352);
      if (warp == 9 && lane == 0) {
#pragma unroll 1
        for (int i = 0; i < 14; i++) {
          const int ex = i >= 7, p = ex ? i - 7 : i;
          if (p >= 5) continue;
          mbar_wait(sb + OFF_PUB + 8 * p, ex);
          st_flag(flag_part(ex, g, p) + j, tag);
        }
      } else if (warp >= 10) {
        const int bm = ((g >> 1) << 4) | ((lane & 7) << 1) | (g & 1);
#pragma unroll 1
        for (int i = 0; i < 4; i++) {
          const int ex = i >> 1;
          const int q = ex == 0 ? (warp == 10 ? i : 2) : 2 * (i & 1) + (warp - 10);
          if (ex == 0 && warp == 11 && i == 1) continue;
          const int p0 = grp_first(ex, q), np = grp_size(ex, q);
          mbar_wait(sb + OFF_PUB, ex);
          const bool mine = (lane >> 3) >= np || (lane & 7) == j;
          uint32_t spins = 0;
          bool ok;
          do {
            const unsigned want = p0 + (lane >> 3) >= 5 ? tag * 8 : tag;
            unsigned v = want;
            if (!mine) asm volatile("ld.relaxed.gpu.global.u32 %0, [%1];" : "=r"(v) : "l"(flag_part(ex, g, p0 + (lane >> 3)) + (lane & 7)) : "memory");
            ok = __all_sync(0xffffffff, v == want);
          } while (!ok && ++spins < (1u << 24));
          mbar_wait(sb + OFF_PUB + 8 * (ex || q == 0 ? p0 + np - 1 : 6), ex);
          if (lane == 8) mbar_expect_tx(sb + OFF_PFG + 8 * q, 8 * np * 2048);
          if (lane < 8) bulk_load(sb + grp_base(ex, q) + lane * np * 2048, g_part + (((size_t)bm * 8 + j) * 7 + p0) * 128, np * 2048, sb + OFF_PFG + 8 * q);
        }
      }
    }
  } else {
    asm volatile("setmaxnreg.inc.sync.aligned.u32 240;");
    const int wg = warp >> 2;
    const int tid = threadIdx.x;
    const unsigned tag = g_epoch[b] + 1;
    uint32_t cmask = 0;
    auto wait_full = [&](int s) { mbar_wait(full + 8 * s, (cmask >> s) & 1); cmask ^= 1u << s; };
    auto release = [&](int s) {
      if (lane == 0) mbar_arrive(empty + 8 * s);
      if (lane == 1) mbar_arrive_remote(empty + 8 * s, rank ^ 1);
    };
    const uint32_t mbase = (uint32_t)(warp * 16 + (lane & 7) + ((lane >> 3) & 1) * 8) * 128;
    const uint32_t mxor = (uint32_t)((lane >> 4) ^ (lane & 7));
    auto frag_addr = [&](uint32_t chunk_base, int t) { return chunk_base + mbase + ((mxor ^ (uint32_t)(2 * t)) << 4); };
    {
      if (b < 84) {
        float acc[8];
#pragma unroll
        for (int e = 0; e < 8; e++) acc[e] = 0.f;
#pragma unroll
        for (int i = 0; i < 7; i++) {
          const float cf = __bfloat162float(cv[i]);
          const float sc = round_bf16(__fdividef(cf, 1.f + __expf(-cf)));
          acc[0] = fmaf(sc, bf_lo(wv[i].x), acc[0]); acc[1] = fmaf(sc, bf_hi(wv[i].x), acc[1]);
          acc[2] = fmaf(sc, bf_lo(wv[i].y), acc[2]); acc[3] = fmaf(sc, bf_hi(wv[i].y), acc[3]);
          acc[4] = fmaf(sc, bf_lo(wv[i].z), acc[4]); acc[5] = fmaf(sc, bf_hi(wv[i].z), acc[5]);
          acc[6] = fmaf(sc, bf_lo(wv[i].w), acc[6]); acc[7] = fmaf(sc, bf_hi(wv[i].w), acc[7]);
        }
        if (lane == 0 && acc[0] + acc[7] != 1.2345678e33f) mbar_arrive(sb + OFF_GV);
#pragma unroll
        for (int o = 4; o < 32; o <<= 1)
#pragma unroll
          for (int e = 0; e < 8; e++) acc[e] += __shfl_xor_sync(0xffffffff, acc[e], o);
        float* scr = reinterpret_cast<float*>(smem_raw + OFF_GEMV);
        if (lane < 4) {
          *reinterpret_cast<float4*>(scr + warp * 32 + lane * 8) = make_float4(acc[0], acc[1], acc[2], acc[3]);
          *reinterpret_cast<float4*>(scr + warp * 32 + lane * 8 + 4) = make_float4(acc[4], acc[5], acc[6], acc[7]);
        }
        named_sync(5, 256);
        if (tid < 32) {
          float s = 0.f;
#pragma unroll
          for (int w = 0; w < 8; w++) s += scr[w * 32 + tid];
          s = round_bf16(s);
          asm volatile("red.relaxed.gpu.global.max.u64 [%0], %1;" ::"l"(&g_mod[b * 32 + tid]), "l"(((unsigned long long)tag << 32) | __float_as_uint(s)) : "memory");
        }
      }
      auto chunk_base = [&](int q) { return q < 6 ? sb + q * 16384 : ring + 3 * SLOT; };
      uint32_t xf[112];
      {
        float dq0[2][4], dq1[2][4], ds[2][4];
#pragma unroll
        for (int u = 0; u < 2; u++)
#pragma unroll
          for (int e = 0; e < 4; e++) { dq0[u][e] = 0.f; dq1[u][e] = 0.f; ds[u][e] = 0.f; }
#pragma unroll
        for (int q = 0; q < 7; q++) {
          mbar_wait(sb + OFF_HFULL + 8 * q, 0);
#pragma unroll
          for (int t = 0; t < 4; t++) {
            uint32_t* a = xf + 16 * q + 4 * t;
            ldsm4(frag_addr(chunk_base(q), t), a[0], a[1], a[2], a[3]);
            mma16816(dq0[t & 1], a[0], a[1], a[2], a[3], a[0], a[2]);
            mma16816(dq1[t & 1], a[0], a[1], a[2], a[3], a[1], a[3]);
            mma16816(ds[t & 1], a[0], a[1], a[2], a[3], 0x3F803F80u, 0x3F803F80u);
          }
        }
        const int i = lane >> 2;
        const float qa = (i & 1) ? dq0[0][1] + dq0[1][1] : dq0[0][0] + dq0[1][0];
        const float qb = (i & 1) ? dq1[0][3] + dq1[1][3] : dq1[0][2] + dq1[1][2];
        const int src_q = 4 * i + (i >> 1);
        const float q_[2] = {__shfl_sync(0xffffffff, qa, src_q), __shfl_sync(0xffffffff, qb, src_q)};
        const float s_[2] = {ds[0][0] + ds[1][0], ds[0][2] + ds[1][2]};
        uint32_t mul2[2], add2[2];
#pragma unroll
        for (int hh = 0; hh < 2; hh++) {
          const float mean = s_[hh] * (1.f / DM);
          const float rstd = rsqrtf(fmaxf(q_[hh] * (1.f / DM) - mean * mean, 0.f) + 1e-5f);
          mul2[hh] = pack_bf16(rstd, rstd);
          add2[hh] = pack_bf16(-mean * rstd, -mean * rstd);
        }
#pragma unroll
        for (int e = 0; e < 112; e++) xf[e] = hfma2_bf16(xf[e], mul2[e & 1], add2[e & 1]);
      }
      {
        const int n0 = tid * 2, n1 = tid < 192 ? n0 + 512 : n0;
        uint4 w0, w1;
        uint32_t spins = 0;
        do {
          asm volatile("ld.relaxed.gpu.global.v4.u32 {%0, %1, %2, %3}, [%4];" : "=r"(w0.x), "=r"(w0.y), "=r"(w0.z), "=r"(w0.w) : "l"(&g_mod[n0]) : "memory");
          asm volatile("ld.relaxed.gpu.global.v4.u32 {%0, %1, %2, %3}, [%4];" : "=r"(w1.x), "=r"(w1.y), "=r"(w1.z), "=r"(w1.w) : "l"(&g_mod[n1]) : "memory");
        } while ((w0.y != tag || w0.w != tag || w1.y != tag || w1.w != tag) && ++spins < (1u << 24));
#pragma unroll
        for (int u = 0; u < 2; u++) {
          const int n = u ? n1 : n0;
          const uint4 w = u ? w1 : w0;
          const bool sc = n >= DM;
          const int c = sc ? n - DM : n;
          const int word = (c >> 4) * 8 + ((c & 7) >> 1) * 2 + ((c >> 3) & 1);
          const float one = sc ? 1.f : 0.f;
          *reinterpret_cast<uint32_t*>(smem_raw + (sc ? OFF_V0 : OFF_V1) + word * 4) = pack_bf16(one + __uint_as_float(w.x), one + __uint_as_float(w.z));
        }
      }
      named_sync(5, 256);
#pragma unroll
      for (int k = 0; k < 28; k++) {
        uint2 gv, sv;
        asm volatile("ld.shared.v2.u32 {%0, %1}, [%2];" : "=r"(gv.x), "=r"(gv.y) : "r"(sb + OFF_V0 + (k * 8 + (lane & 3) * 2) * 4) : "memory");
        asm volatile("ld.shared.v2.u32 {%0, %1}, [%2];" : "=r"(sv.x), "=r"(sv.y) : "r"(sb + OFF_V1 + (k * 8 + (lane & 3) * 2) * 4) : "memory");
        stsm4(frag_addr(chunk_base(k >> 2), k & 3), hfma2_bf16(xf[4 * k], gv.x, sv.x), hfma2_bf16(xf[4 * k + 1], gv.x, sv.x),
              hfma2_bf16(xf[4 * k + 2], gv.y, sv.y), hfma2_bf16(xf[4 * k + 3], gv.y, sv.y));
      }
      named_arrive(7, 352);
      fence_async_smem();
      named_sync(3 + wg, 128);
    }
    cluster_wait();
    if (wg == 0) named_arrive(1, 256);
    uint32_t q[32];
    {
      float acc[128];
      uint32_t q2[64];
      const uint32_t dA = dlo(sb + wg * 8192, 16), dB = dlo(ring, 8192);
      int s = 0;
#pragma unroll 1
      for (int ps = 0; ps < 2; ps++) {
        int sprev = 0;
#pragma unroll 1
        for (int kc = 0; kc < 7; kc++) {
          wait_full(s);
          const uint32_t a = dA + ((kc < 6 ? kc * 16384 : OFF_RING + 3 * SLOT) >> 4), bb = dB + s * (SLOT >> 4);
          named_sync(1 + wg, 256);
          fence_regs(acc);
          wg_fence();
#pragma unroll
          for (int k = 0; k < 4; k++) wgmma_n256_ss_tb(acc, a, k * 2, bb, k * 128, (kc | k) != 0);
          wg_commit();
          named_arrive(1 + (wg ^ 1), 256);
          if (kc > 0) { wg_wait<1>(); release(sprev); }
          sprev = s;
          s = s == 2 ? 0 : s + 1;
        }
        wg_wait<0>();
        fence_regs(acc);
        release(sprev);
        if (ps == 0) {
#pragma unroll
          for (int e = 0; e < 64; e++) q2[e] = pack_bf16(acc[2 * e], acc[2 * e + 1]);
        }
      }
      release(3);
#pragma unroll
      for (int t = 0; t < 16; t++)
        stsm4(frag_addr(sb + OFF_SA + (t >> 2) * 16384, t & 3), q2[4 * t], q2[4 * t + 1], q2[4 * t + 2], q2[4 * t + 3]);
#pragma unroll
      for (int e = 0; e < 32; e++) q[e] = pack_bf16(acc[2 * e], acc[2 * e + 1]);
#pragma unroll
      for (int t = 8; t < 16; t++)
        stsm4(frag_addr(sb + OFF_QB + ((t >> 2) & 1) * 16384, t & 3), pack_bf16(acc[8 * t], acc[8 * t + 1]), pack_bf16(acc[8 * t + 2], acc[8 * t + 3]),
              pack_bf16(acc[8 * t + 4], acc[8 * t + 5]), pack_bf16(acc[8 * t + 6], acc[8 * t + 7]));
      fence_async_smem();
      named_sync(3 + wg, 128);
    }
    uint32_t o2[64];
    {
      float o[128];
#pragma unroll
      for (int i = 0; i < 128; i++) o[i] = 0.f;
      float s[32];
      uint32_t p[16];
      float m0 = -INFINITY, m1 = -INFINITY, l0 = 0.f, l1 = 0.f, a0 = 1.f, a1 = 1.f, lp0 = 1.f, lp1 = 1.f;
      bool need = false;
      uint32_t dQ = dlo(sb + OFF_QB + wg * 8192, 16);
      const uint32_t dK = dlo(ring, 16), dV = dlo(ring, 8192);
      auto issue_qk = [&](int kslot) {
        const uint32_t kb = dK + kslot * (SLOT >> 4);
#pragma unroll
        for (int k = 0; k < 16; k++) {
          const uint32_t bo = ((k >> 2) * 8192 + (k & 3) * 32) >> 4;
          if (k < 8) wgmma_n64_rs(s, q[4 * k], q[4 * k + 1], q[4 * k + 2], q[4 * k + 3], kb, bo, k > 0);
          else wgmma_n64_ss(s, dQ, (((k - 8) >> 2) * 16384 + (k & 3) * 32) >> 4, kb, bo, 1);
        }
        wg_commit();
      };
      auto softmax = [&]() {
        float x0 = fmaxf(s[0], s[1]), x1 = fmaxf(s[2], s[3]);
#pragma unroll
        for (int gq = 1; gq < 8; gq++) {
          x0 = fmaxf(x0, fmaxf(s[4 * gq], s[4 * gq + 1]));
          x1 = fmaxf(x1, fmaxf(s[4 * gq + 2], s[4 * gq + 3]));
        }
        need = __any_sync(0xffffffff, x0 > m0 + TAU || x1 > m1 + TAU);
        if (need) {
          x0 = fmaxf(x0, m0); x1 = fmaxf(x1, m1);
          x0 = fmaxf(x0, __shfl_xor_sync(0xffffffff, x0, 1));
          x1 = fmaxf(x1, __shfl_xor_sync(0xffffffff, x1, 1));
          x0 = fmaxf(x0, __shfl_xor_sync(0xffffffff, x0, 2));
          x1 = fmaxf(x1, __shfl_xor_sync(0xffffffff, x1, 2));
          a0 = ex2((m0 - x0) * SL2); a1 = ex2((m1 - x1) * SL2);
          m0 = x0; m1 = x1;
          l0 *= a0; l1 *= a1;
        }
        const float n0 = m0 * SL2, n1 = m1 * SL2;
        float r0 = 0.f, r1 = 0.f;
#pragma unroll
        for (int gq = 0; gq < 8; gq++) {
          s[4 * gq] = ex2(fmaf(s[4 * gq], SL2, -n0));
          s[4 * gq + 1] = ex2(fmaf(s[4 * gq + 1], SL2, -n0));
          s[4 * gq + 2] = ex2(fmaf(s[4 * gq + 2], SL2, -n1));
          s[4 * gq + 3] = ex2(fmaf(s[4 * gq + 3], SL2, -n1));
          r0 += s[4 * gq] + s[4 * gq + 1];
          r1 += s[4 * gq + 2] + s[4 * gq + 3];
        }
        l0 += r0; l1 += r1;
      };
      wait_full(2);
      named_sync(1 + wg, 256);
      fence_regs(s); fence_regs(q);
      wg_fence();
      issue_qk(2);
      named_arrive(1 + (wg ^ 1), 256);
      wg_wait<0>();
      fence_regs(s);
      release(2);
      softmax();
      need = false;
#pragma unroll
      for (int e = 0; e < 16; e++) p[e] = pack_bf16(s[2 * e], s[2 * e + 1]);
#pragma unroll 1
      for (int t = 1; t < 64; t++) {
        const int kslot = (t & 1) ? 0 : 2, vslot = (t & 1) ? 3 : 1;
        if (t == 32) {
#pragma unroll
          for (int u = 0; u < 8; u++) ldsm4(frag_addr(sb + OFF_SA + (u >> 2) * 16384, u & 3), q[4 * u], q[4 * u + 1], q[4 * u + 2], q[4 * u + 3]);
          dQ = dlo(sb + OFF_SB + wg * 8192, 16);
          lp0 = l0; lp1 = l1; l0 = 0.f; l1 = 0.f; m0 = -INFINITY; m1 = -INFINITY;
        }
        wait_full(kslot);
        named_sync(1 + wg, 256);
        fence_regs(s); fence_regs(q);
        wg_fence();
        issue_qk(kslot);
        fence_regs(o);
        if (need) {
#pragma unroll
          for (int gq = 0; gq < 32; gq++) { o[4 * gq] *= a0; o[4 * gq + 1] *= a0; o[4 * gq + 2] *= a1; o[4 * gq + 3] *= a1; }
        }
        wait_full(vslot);
        fence_regs(o); fence_regs(p);
        wg_fence();
        {
          const uint32_t vb = dV + vslot * (SLOT >> 4);
#pragma unroll
          for (int k = 0; k < 4; k++) wgmma_n256_rs_tb(o, p[4 * k], p[4 * k + 1], p[4 * k + 2], p[4 * k + 3], vb, k * 128, 1);
        }
        wg_commit();
        named_arrive(1 + (wg ^ 1), 256);
        wg_wait<1>();
        fence_regs(s);
        release(kslot);
        softmax();
        wg_wait<0>();
        fence_regs(o); fence_regs(p);
        release(vslot);
#pragma unroll
        for (int e = 0; e < 16; e++) p[e] = pack_bf16(s[2 * e], s[2 * e + 1]);
        if (t == 32) {
          lp0 += __shfl_xor_sync(0xffffffff, lp0, 1); lp0 += __shfl_xor_sync(0xffffffff, lp0, 2);
          lp1 += __shfl_xor_sync(0xffffffff, lp1, 1); lp1 += __shfl_xor_sync(0xffffffff, lp1, 2);
          const float i0 = 1.f / lp0, i1 = 1.f / lp1;
#pragma unroll
          for (int u = 0; u < 16; u++)
            stsm4(frag_addr(sb + (u < 8 ? OFF_SA : OFF_QB) + ((u >> 2) & 1) * 16384, u & 3), pack_bf16(o[8 * u] * i0, o[8 * u + 1] * i0),
                  pack_bf16(o[8 * u + 2] * i1, o[8 * u + 3] * i1), pack_bf16(o[8 * u + 4] * i0, o[8 * u + 5] * i0), pack_bf16(o[8 * u + 6] * i1, o[8 * u + 7] * i1));
          fence_async_smem();
        }
      }
      fence_regs(o);
      if (need) {
#pragma unroll
        for (int gq = 0; gq < 32; gq++) { o[4 * gq] *= a0; o[4 * gq + 1] *= a0; o[4 * gq + 2] *= a1; o[4 * gq + 3] *= a1; }
      }
      wait_full(1);
      fence_regs(o); fence_regs(p);
      wg_fence();
#pragma unroll
      for (int k = 0; k < 4; k++) wgmma_n256_rs_tb(o, p[4 * k], p[4 * k + 1], p[4 * k + 2], p[4 * k + 3], dV, (1 * SLOT + k * 2048) >> 4, 1);
      wg_commit();
      wg_wait<0>();
      fence_regs(o);
      release(1);
      l0 += __shfl_xor_sync(0xffffffff, l0, 1); l0 += __shfl_xor_sync(0xffffffff, l0, 2);
      l1 += __shfl_xor_sync(0xffffffff, l1, 1); l1 += __shfl_xor_sync(0xffffffff, l1, 2);
      const float i0 = 1.f / l0, i1 = 1.f / l1;
#pragma unroll
      for (int gq = 0; gq < 32; gq++) {
        o2[2 * gq] = pack_bf16(o[4 * gq] * i0, o[4 * gq + 1] * i0);
        o2[2 * gq + 1] = pack_bf16(o[4 * gq + 2] * i1, o[4 * gq + 3] * i1);
      }
    }
    named_sync(3 + wg, 128);
    auto pp_enter = [&]() { named_sync(1 + wg, 256); };
    auto pp_leave = [&]() { named_arrive(1 + (wg ^ 1), 256); };
    auto flush = [&](float (&acc)[32], int ex, int ps) {
      fence_regs(acc);
      uint4* dst = g_part + (((size_t)b * 8 + warp) * 7 + ps) * 128 + lane;
#pragma unroll
      for (int t = 0; t < 4; t++) {
        const uint32_t wp = pack_bf16(acc[8 * t], acc[8 * t + 1]);
        const uint32_t w0 = ex == 0 ? (wp | 1u) : ((wp + (t & 1)) & ~1u);
        __stcg(dst + t * 32, make_uint4(w0, pack_bf16(acc[8 * t + 2], acc[8 * t + 3]),
                                        pack_bf16(acc[8 * t + 4], acc[8 * t + 5]), pack_bf16(acc[8 * t + 6], acc[8 * t + 7])));
      }
      __syncwarp();
      if (lane == 0) {
        mbar_arrive(sb + OFF_PUB + 8 * ps);
        if (ps >= 5) asm volatile("red.relaxed.gpu.global.add.u32 [%0], 1;" ::"l"(flag_part(ex, g, ps) + j) : "memory");
      }
    };

    {
      float accA[32], accB[32];
      const uint32_t dA = dlo(sb + wg * 8192, 16), dB = dlo(ring, 16);
      auto tile0 = [&](float (&acc)[32], int s) {
        wait_full(s);
        pp_enter();
        fence_regs(acc);
        wg_fence();
#pragma unroll
        for (int k = 0; k < 16; k++)
          wgmma_n64_ss_tb(acc, dA, ((k < 8 ? OFF_SA : OFF_QB) + ((k >> 2) & 1) * 16384 + (k & 3) * 32) >> 4, dB, (s * SLOT + k * 2048) >> 4, k > 0);
        wg_commit();
        pp_leave();
      };
      auto tile1 = [&](float (&acc)[32], int s) {
        wait_full(s);
        pp_enter();
        fence_regs(acc);
        wg_fence();
#pragma unroll
        for (int k = 0; k < 16; k++)
          wgmma_n64_rs_tb(acc, o2[4 * k], o2[4 * k + 1], o2[4 * k + 2], o2[4 * k + 3], dB, (s * SLOT + k * 2048) >> 4, 1);
        wg_commit();
        pp_leave();
      };
      tile0(accA, 2); tile1(accA, 3); wg_wait<1>(); release(2);
#pragma unroll 1
      for (int it = 0; it < 3; it++) {
        tile0(accB, 0); wg_wait<1>(); release(3); flush(accA, 0, 2 * it);
        tile1(accB, 1); wg_wait<1>(); release(0);
        tile0(accA, 2); wg_wait<1>(); release(1); flush(accB, 0, 2 * it + 1);
        tile1(accA, 3); wg_wait<1>(); release(2);
      }
      wg_wait<0>(); release(3); flush(accA, 0, 6);
    }
    uint32_t pparity = 0;
    const int frow = g * 128 + j * 16 + (lane >> 2);
    const int fcol = warp * 64 + (lane & 3) * 2;
    auto sum_partials = [&](float (&v)[32], int ex) {
      const int q = grp_of(ex, warp);
      const uint32_t stride = grp_size(ex, q) * 2048, blk = sb + grp_base(ex, q) + (warp - grp_first(ex, q)) * 2048;
      mbar_wait(sb + OFF_PFG + 8 * q, ex == 0 || q == 3 ? 0 : 1);
      bool stale;
      uint32_t tries = 0;
      do {
#pragma unroll
        for (int e = 0; e < 32; e++) v[e] = 0.f;
        uint32_t tags_and = 1u, tags_or = 0u;
#pragma unroll 2
        for (int m = 0; m < 8; m++) {
#pragma unroll
          for (int t = 0; t < 4; t++) {
            const uint4 w = lds128(blk + lane * 16 + m * stride + t * 512);
            tags_and &= w.x; tags_or |= w.x;
            v[8 * t] += bf_lo(w.x); v[8 * t + 1] += bf_hi(w.x); v[8 * t + 2] += bf_lo(w.y); v[8 * t + 3] += bf_hi(w.y);
            v[8 * t + 4] += bf_lo(w.z); v[8 * t + 5] += bf_hi(w.z); v[8 * t + 6] += bf_lo(w.w); v[8 * t + 7] += bf_hi(w.w);
          }
        }
        stale = __any_sync(0xffffffff, ex == 0 ? !(tags_and & 1u) : (tags_or & 1u) != 0);
        if (stale) {
          const uint32_t bar = sb + OFF_PFULL + 8 * warp;
          fence_async_smem();
          __syncwarp();
          if (lane == 8) mbar_expect_tx(bar, 8 * 2048);
          if (lane < 8) {
            const int bm = ((g >> 1) << 4) | (lane << 1) | (g & 1);
            bulk_load(blk + lane * stride, g_part + (((size_t)bm * 8 + j) * 7 + warp) * 128, 2048, bar);
          }
          mbar_wait(bar, pparity);
          pparity ^= 1;
        }
      } while (stale && ++tries < (1u << 20));
    };
    auto lds32 = [&](uint32_t a) { uint32_t w; asm volatile("ld.shared.u32 %0, [%1];" : "=r"(w) : "r"(a) : "memory"); return w; };
    {
      float v[32];
      uint32_t gw2[16], sw2[16];
      float2* red = reinterpret_cast<float2*>(smem_raw + OFF_SA + 16384);
      if (warp < 7) {
        uint32_t xr[16];
#pragma unroll
        for (int e = 0; e < 16; e++)
          xr[e] = __ldg(reinterpret_cast<const uint32_t*>(prm.x + (size_t)(frow + 8 * (e & 1)) * DM + fcol + 16 * (e >> 2) + 8 * ((e >> 1) & 1)));
        named_sync(8, 352);
        sum_partials(v, 0);
        float s0 = 0.f, s1 = 0.f, q0 = 0.f, q1 = 0.f;
#pragma unroll
        for (int e = 0; e < 16; e++) {
          const uint32_t gw = lds32(sb + OFF_V0 + (fcol + 16 * (e >> 2) + 8 * ((e >> 1) & 1)) * 2);
          v[2 * e] = fmaf(bf_lo(gw), v[2 * e], bf_lo(xr[e])); v[2 * e + 1] = fmaf(bf_hi(gw), v[2 * e + 1], bf_hi(xr[e]));
          if (e & 1) { s1 += v[2 * e] + v[2 * e + 1]; q1 = fmaf(v[2 * e], v[2 * e], q1); q1 = fmaf(v[2 * e + 1], v[2 * e + 1], q1); }
          else { s0 += v[2 * e] + v[2 * e + 1]; q0 = fmaf(v[2 * e], v[2 * e], q0); q0 = fmaf(v[2 * e + 1], v[2 * e + 1], q0); }
        }
#pragma unroll
        for (int o = 1; o < 4; o <<= 1) {
          s0 += __shfl_xor_sync(0xffffffff, s0, o); s1 += __shfl_xor_sync(0xffffffff, s1, o);
          q0 += __shfl_xor_sync(0xffffffff, q0, o); q1 += __shfl_xor_sync(0xffffffff, q1, o);
        }
        if ((lane & 3) == 0) { red[warp * 16 + (lane >> 2)] = make_float2(s0, q0); red[warp * 16 + 8 + (lane >> 2)] = make_float2(s1, q1); }
#pragma unroll
        for (int e = 0; e < 16; e++) {
          const int co = fcol + 16 * (e >> 2) + 8 * ((e >> 1) & 1);
          gw2[e] = lds32(sb + OFF_V2 + co * 2); sw2[e] = lds32(sb + OFF_V1 + co * 2);
        }
      } else {
        named_sync(8, 352);
      }
      named_sync(5, 256);
      if (warp < 7) {
        float s0 = 0.f, s1 = 0.f, q0 = 0.f, q1 = 0.f;
#pragma unroll
        for (int w = 0; w < 7; w++) {
          const float2 a = red[w * 16 + (lane >> 2)], c = red[w * 16 + 8 + (lane >> 2)];
          s0 += a.x; q0 += a.y; s1 += c.x; q1 += c.y;
        }
        const float mean0 = s0 * (1.f / DM), mean1 = s1 * (1.f / DM);
        const float rs0 = rsqrtf(fmaxf(q0 * (1.f / DM) - mean0 * mean0, 0.f) + 1e-5f), rs1 = rsqrtf(fmaxf(q1 * (1.f / DM) - mean1 * mean1, 0.f) + 1e-5f);
#pragma unroll
        for (int e = 0; e < 16; e++) {
          const int co = fcol + 16 * (e >> 2) + 8 * ((e >> 1) & 1);
          const float mean = (e & 1) ? mean1 : mean0, rs = (e & 1) ? rs1 : rs0;
          const uint32_t hv = pack_bf16(fmaf((v[2 * e] - mean) * rs, bf_lo(gw2[e]), bf_lo(sw2[e])), fmaf((v[2 * e + 1] - mean) * rs, bf_hi(gw2[e]), bf_hi(sw2[e])));
          asm volatile("st.shared.u32 [%0], %1;" ::"r"(sb + OFF_QB + ((lane >> 2) + 8 * (e & 1)) * 912 + co * 2), "r"(hv) : "memory");
        }
        fence_async_smem();
      }
      named_sync(5, 256);
      if (lane < 2) {
        bulk_store(g_h2 + (size_t)(g * 128 + j * 16 + warp * 2 + lane) * DM, sb + OFF_QB + (warp * 2 + lane) * 912, DM * 2);
        bulk_wait<0>();
        asm volatile("red.release.gpu.global.add.u32 [%0], 1;" ::"l"(flag_h2(g) + j) : "memory");
        mbar_arrive(sb + OFF_HS);
      }
      __syncwarp();
      if (warp < 7) {
        float4* xp = reinterpret_cast<float4*>(g_x1) + ((size_t)b * 7 + warp) * 256 + lane;
#pragma unroll
        for (int e = 0; e < 8; e++) xp[e * 32] = make_float4(v[4 * e], v[4 * e + 1], v[4 * e + 2], v[4 * e + 3]);
      }
      if (tid < 224) { const float2 t = load_mod_pair(5 * DM + 2 * tid, tag); *reinterpret_cast<uint32_t*>(smem_raw + OFF_V0 + tid * 4) = pack_bf16(t.x, t.y); }
    }
    {
      uint32_t a1[56];
      float acc[112];
      {
        const uint32_t dA = dlo(sb + wg * 8192, 16), dB = dlo(ring, 8192);
        int s = 0, sprev = 0;
#pragma unroll 1
        for (int i = 0; i < 7; i++) {
          mbar_wait(sb + OFF_HFULL + 8 * i, 1);
          wait_full(s);
          const uint32_t a = dA + ((i < 6 ? i * 16384 : OFF_RING + 3 * SLOT) >> 4), bb = dB + s * (SLOT >> 4);
          pp_enter();
          fence_regs(acc);
          wg_fence();
#pragma unroll
          for (int k = 0; k < 4; k++) wgmma_n224_ss_tb(acc, a, k * 2, bb, k * 128, (i | k) != 0);
          wg_commit();
          pp_leave();
          if (i > 0) { wg_wait<1>(); release(sprev); }
          sprev = s;
          s = s == 2 ? 0 : s + 1;
        }
        wg_wait<0>();
        fence_regs(acc);
        release(sprev);
        release(3);
      }
      auto silu = [&](int e0, int e1) {
#pragma unroll
        for (int e = e0; e < e1; e++) {
          const float h0 = 0.5f * acc[2 * e], h1 = 0.5f * acc[2 * e + 1];
          a1[e] = pack_bf16(fmaf(h0, tanh_fast(h0), h0), fmaf(h1, tanh_fast(h1), h1));
        }
      };
      float accA[32], accB[32];
      const uint32_t dB = dlo(sb, 16);
      auto tile_base = [&](int v) {
        const int s = v < 2 ? v + 1 : (v == 2 ? 0 : v);
        wait_full(s);
        return dB + ((s < 4 ? OFF_RING + s * SLOT : (s - 4) * SLOT) >> 4);
      };
      auto tile = [&](float (&acc2)[32], int v) {
        const uint32_t bb = tile_base(v);
        pp_enter();
        fence_regs(acc2);
        wg_fence();
#pragma unroll
        for (int k = 0; k < 14; k++) wgmma_n64_rs_tb(acc2, a1[4 * k], a1[4 * k + 1], a1[4 * k + 2], a1[4 * k + 3], bb, k * 128, k > 0);
        wg_commit();
        pp_leave();
      };
      silu(0, 28);
      {
        const uint32_t b0 = tile_base(0), b1 = tile_base(1);
        pp_enter();
        fence_regs(accA); fence_regs(accB);
        wg_fence();
#pragma unroll
        for (int k = 0; k < 7; k++) wgmma_n64_rs_tb(accA, a1[4 * k], a1[4 * k + 1], a1[4 * k + 2], a1[4 * k + 3], b0, k * 128, k > 0);
#pragma unroll
        for (int k = 0; k < 7; k++) wgmma_n64_rs_tb(accB, a1[4 * k], a1[4 * k + 1], a1[4 * k + 2], a1[4 * k + 3], b1, k * 128, k > 0);
        wg_commit();
        pp_leave();
        silu(28, 56);
        pp_enter();
        wg_fence();
#pragma unroll
        for (int k = 7; k < 14; k++) wgmma_n64_rs_tb(accA, a1[4 * k], a1[4 * k + 1], a1[4 * k + 2], a1[4 * k + 3], b0, k * 128, 1);
        wg_commit();
#pragma unroll
        for (int k = 7; k < 14; k++) wgmma_n64_rs_tb(accB, a1[4 * k], a1[4 * k + 1], a1[4 * k + 2], a1[4 * k + 3], b1, k * 128, 1);
        wg_commit();
        pp_leave();
        wg_wait<1>(); flush(accA, 1, 0);
        tile(accA, 2); wg_wait<1>(); flush(accB, 1, 1);
      }
#pragma unroll 1
      for (int it = 1; it < 3; it++) {
        tile(accB, 2 * it + 1); wg_wait<1>(); flush(accA, 1, 2 * it);
        tile(accA, 2 * it + 2); wg_wait<1>(); flush(accB, 1, 2 * it + 1);
      }
      wg_wait<0>(); flush(accA, 1, 6);
    }
    {
      float4 x1[8];
      if (warp < 7) {
        const float4* xp = reinterpret_cast<const float4*>(g_x1) + ((size_t)b * 7 + warp) * 256 + lane;
#pragma unroll
        for (int e = 0; e < 8; e++) x1[e] = __ldcg(xp + e * 32);
      }
      named_sync(5, 256);
      if (warp < 7) {
        float v[32];
        sum_partials(v, 1);
#pragma unroll
        for (int e = 0; e < 16; e++) {
          const int co = fcol + 16 * (e >> 2) + 8 * ((e >> 1) & 1);
          const uint32_t gw = lds32(sb + OFF_V0 + co * 2);
          const float xa = (e & 1) ? x1[e >> 1].z : x1[e >> 1].x, xb = (e & 1) ? x1[e >> 1].w : x1[e >> 1].y;
          *reinterpret_cast<uint32_t*>(prm.out + (size_t)(frow + 8 * (e & 1)) * DM + co) = pack_bf16(fmaf(bf_lo(gw), v[2 * e], xa), fmaf(bf_hi(gw), v[2 * e + 1], xb));
        }
      }
    }
    if (wg == 0) named_sync(1, 256);
    if (tid == 0) g_epoch[b] = tag;
  }
}

typedef CUresult (*EncodeFn)(CUtensorMap*, CUtensorMapDataType, cuuint32_t, void*, const cuuint64_t*, const cuuint64_t*, const cuuint32_t*,
                             const cuuint32_t*, CUtensorMapInterleave, CUtensorMapSwizzle, CUtensorMapL2promotion, CUtensorMapFloatOOBfill);

CUtensorMap make_map3(EncodeFn enc, const void* base, uint64_t rows, uint64_t cols, uint32_t box_rows, uint32_t box_chunks) {
  CUtensorMap m;
  cuuint64_t dims[3] = {64, rows, cols / 64};
  cuuint64_t str[2] = {cols * 2, 128};
  cuuint32_t box[3] = {64, box_rows, box_chunks};
  cuuint32_t es[3] = {1, 1, 1};
  enc(&m, CU_TENSOR_MAP_DATA_TYPE_BFLOAT16, 3, const_cast<void*>(base), dims, str, box, es, CU_TENSOR_MAP_INTERLEAVE_NONE,
      CU_TENSOR_MAP_SWIZZLE_128B, CU_TENSOR_MAP_L2_PROMOTION_L2_256B, CU_TENSOR_MAP_FLOAT_OOB_FILL_NONE);
  return m;
}
CUtensorMap make_map2(EncodeFn enc, const void* base, uint64_t rows, uint64_t cols, uint32_t box_rows) {
  CUtensorMap m;
  cuuint64_t dims[2] = {cols, rows};
  cuuint64_t str[1] = {cols * 2};
  cuuint32_t box[2] = {64, box_rows};
  cuuint32_t es[2] = {1, 1};
  enc(&m, CU_TENSOR_MAP_DATA_TYPE_BFLOAT16, 2, const_cast<void*>(base), dims, str, box, es, CU_TENSOR_MAP_INTERLEAVE_NONE,
      CU_TENSOR_MAP_SWIZZLE_128B, CU_TENSOR_MAP_L2_PROMOTION_L2_256B, CU_TENSOR_MAP_FLOAT_OOB_FILL_NONE);
  return m;
}

}

extern "C" void kernel_launch(void* const* d_in, const int* in_sizes, int n_in, void* d_out, int out_size) {
  (void)in_sizes; (void)n_in; (void)out_size;
  const bf16* x = (const bf16*)d_in[0];
  const bf16* kc = (const bf16*)d_in[1];
  const bf16* vc = (const bf16*)d_in[2];
  const bf16* wq = (const bf16*)d_in[3];
  const bf16* wo = (const bf16*)d_in[4];
  const bf16* w1 = (const bf16*)d_in[6];
  const bf16* w2 = (const bf16*)d_in[7];
  const bf16* c = (const bf16*)d_in[8];
  const bf16* wmod = (const bf16*)d_in[9];

  static EncodeFn enc = nullptr;
  static void* p_h2 = nullptr;
  if (!enc) {
    void* fn = nullptr;
    cudaDriverEntryPointQueryResult qr;
    cudaGetDriverEntryPoint("cuTensorMapEncodeTiled", &fn, cudaEnableDefault, &qr);
    enc = (EncodeFn)fn;
    cudaGetSymbolAddress(&p_h2, g_h2);
    cudaFuncSetAttribute(fused_kernel, cudaFuncAttributeMaxDynamicSharedMemorySize, SMEM_BYTES);
  }
  CUtensorMap tmK = make_map3(enc, kc, (uint64_t)NH * SEQ, DH, 64, 2);
  CUtensorMap tmV = make_map3(enc, vc, (uint64_t)NH * SEQ, DH, 64, 2);
  CUtensorMap tmWq = make_map3(enc, wq, DM, NH * DH, 64, 2);
  CUtensorMap tmWo = make_map2(enc, wo, NH * DH, DM, 128);
  CUtensorMap tmW1 = make_map2(enc, w1, DM, FF, 64);
  CUtensorMap tmW2 = make_map2(enc, w2, FF, DM, 112);
  CUtensorMap tmX = make_map3(enc, x, SEQ, DM, 128, 1);
  CUtensorMap tmH2 = make_map3(enc, p_h2, SEQ, DM, 128, 1);
  Params prm{x, c, wmod, (bf16*)d_out};

  cudaLaunchConfig_t cfg = {};
  cfg.gridDim = dim3(NCTA);
  cfg.blockDim = dim3(384);
  cfg.dynamicSmemBytes = SMEM_BYTES;
  cfg.stream = cudaStreamPerThread;
  cudaLaunchAttribute at[1];
  at[0].id = cudaLaunchAttributeClusterDimension;
  at[0].val.clusterDim.x = 2; at[0].val.clusterDim.y = 1; at[0].val.clusterDim.z = 1;
  cfg.attrs = at; cfg.numAttrs = 1;
  cudaLaunchKernelEx(&cfg, fused_kernel, tmK, tmV, tmWq, tmWo, tmW1, tmW2, tmX, tmH2, prm);
}
```
